```python
import torch

def _softmax(x, axis=-1):
    return torch.softmax(x, dim=axis)
def _gelu(x):
    return torch.nn.functional.gelu(x, approximate="tanh")
def _silu(x):
    return torch.nn.functional.silu(x)
def _sigmoid(x):
    return torch.sigmoid(x)
def _layernorm(x, axis=-1, eps=1e-5):
    m = x.mean(dim=axis, keepdim=True)
    v = x.var(dim=axis, keepdim=True, unbiased=False)
    return (x - m) / torch.sqrt(v + eps)
def _scatter_add(tgt, idx, src, axis=0):
    return tgt.clone().index_add_(axis, idx, src)
def _segment_sum(src, seg, n):
    out = torch.zeros((n,) + src.shape[1:], dtype=src.dtype)
    return out.index_add_(0, seg, src)
def _pad(x, pw):
    flat = tuple(v for pair in reversed(pw) for v in pair)
    return torch.nn.functional.pad(x, flat)

kernel_name = 'standalone__layernorm_linear__prompt'

def setup_inputs():

    _w = (lambda a: (lambda t: t.to(torch.bfloat16) if t.is_floating_point() else t)(torch.as_tensor(a)))
    B, S, D = 2, 2048, 1024
    return {
        "x": _w((lambda *s: torch.randn(*s, dtype=torch.bfloat16) * 0.05)(B, S, D)),
        "g": _w((lambda *s: torch.randn(*s, dtype=torch.bfloat16) * 0.05)(D) + 1.0),
        "b": _w((lambda *s: torch.randn(*s, dtype=torch.bfloat16) * 0.4)(D)),
        "w": _w((lambda *s: torch.randn(*s, dtype=torch.bfloat16) * 0.05)(D, D)),
    }

def reference(x, g, b, w):
    return (_layernorm(x, axis=-1) * g + b) @ w
```

```cpp
#include <cuda_runtime.h>
#include <cuda_bf16.h>
#include <cuda.h>
#include <stdint.h>

namespace {

constexpr int M_ = 4096, N_ = 1024, K_ = 1024;
constexpr int BM = 128, BN = 256, BK = 64;
constexpr int A_BYTES = BM * BK * 2, B_BYTES = BN * BK * 2, STAGE_BYTES = A_BYTES + B_BYTES;
constexpr int NSIDE = 5;
constexpr int LASTC = 15 - NSIDE;
constexpr int SLOT = NSIDE * 512;
constexpr int SKEW = 4;
constexpr float MEAN_LIMIT = 4.f;
constexpr uint32_t SPIN_LIMIT = 1u << 14;
constexpr uint32_t POLL_LIMIT = 1u << 16;

constexpr uint32_t SMEM_BASE = 1024;
constexpr int OFF_G = 4 * STAGE_BYTES;
constexpr int OFF_B = OFF_G + 2048;
constexpr int OFF_SEQ = OFF_B + 2048;
constexpr int OFF_RSTD = OFF_SEQ + 2048;
constexpr int OFF_SIDE = OFF_RSTD + 1024;
constexpr int OFF_BB = OFF_SIDE, OFF_AB = OFF_SIDE + 8192;
constexpr int OFF_PART = OFF_SIDE + 8 * SLOT;
constexpr int OFF_RED = OFF_PART + 2048;
constexpr int OFF_BAR = OFF_RED + 512;
constexpr int SMEM_BYTES = OFF_BAR + 512;

constexpr uint32_t T_PF_XB0 = 350, T_PF_XA1 = 800, T_PF_W1 = 1000, T_PF_XB1 = 1300;
constexpr uint32_t T_TILE1 = 800, T_TILE = 850, T_W = 300, T_XB = 550;
constexpr uint32_t T_COL0 = 500, T_COL = 300;

constexpr int XCH_FLAG = 128, XCH_COL = 256, XCH_ROW = XCH_COL + 4 * N_;
__device__ __align__(128) uint2 g_xch[XCH_ROW + 4 * M_];

__device__ __forceinline__ void wgmma_rs_n256(float* d, const uint32_t* a, uint32_t db, int acc) {
    asm volatile("{\n.reg .pred p;\n.reg .b64 dd;\nsetp.ne.b32 p, %133, 0;\nmov.b64 dd, {%132, 0x40000040};\n"
        "wgmma.mma_async.sync.aligned.m64n256k16.f32.bf16.bf16 "
        "{%0, %1, %2, %3, %4, %5, %6, %7, %8, %9, %10, %11, %12, %13, %14, %15, "
        "%16, %17, %18, %19, %20, %21, %22, %23, %24, %25, %26, %27, %28, %29, %30, %31, "
        "%32, %33, %34, %35, %36, %37, %38, %39, %40, %41, %42, %43, %44, %45, %46, %47, "
        "%48, %49, %50, %51, %52, %53, %54, %55, %56, %57, %58, %59, %60, %61, %62, %63, "
        "%64, %65, %66, %67, %68, %69, %70, %71, %72, %73, %74, %75, %76, %77, %78, %79, "
        "%80, %81, %82, %83, %84, %85, %86, %87, %88, %89, %90, %91, %92, %93, %94, %95, "
        "%96, %97, %98, %99, %100, %101, %102, %103, %104, %105, %106, %107, %108, %109, %110, %111, "
        "%112, %113, %114, %115, %116, %117, %118, %119, %120, %121, %122, %123, %124, %125, %126, %127}, "
        "{%128, %129, %130, %131}, dd, p, 1, 1, 1;\n}\n"
        : "+f"(d[0]), "+f"(d[1]), "+f"(d[2]), "+f"(d[3]), "+f"(d[4]), "+f"(d[5]), "+f"(d[6]), "+f"(d[7]),
          "+f"(d[8]), "+f"(d[9]), "+f"(d[10]), "+f"(d[11]), "+f"(d[12]), "+f"(d[13]), "+f"(d[14]), "+f"(d[15]),
          "+f"(d[16]), "+f"(d[17]), "+f"(d[18]), "+f"(d[19]), "+f"(d[20]), "+f"(d[21]), "+f"(d[22]), "+f"(d[23]),
          "+f"(d[24]), "+f"(d[25]), "+f"(d[26]), "+f"(d[27]), "+f"(d[28]), "+f"(d[29]), "+f"(d[30]), "+f"(d[31]),
          "+f"(d[32]), "+f"(d[33]), "+f"(d[34]), "+f"(d[35]), "+f"(d[36]), "+f"(d[37]), "+f"(d[38]), "+f"(d[39]),
          "+f"(d[40]), "+f"(d[41]), "+f"(d[42]), "+f"(d[43]), "+f"(d[44]), "+f"(d[45]), "+f"(d[46]), "+f"(d[47]),
          "+f"(d[48]), "+f"(d[49]), "+f"(d[50]), "+f"(d[51]), "+f"(d[52]), "+f"(d[53]), "+f"(d[54]), "+f"(d[55]),
          "+f"(d[56]), "+f"(d[57]), "+f"(d[58]), "+f"(d[59]), "+f"(d[60]), "+f"(d[61]), "+f"(d[62]), "+f"(d[63]),
          "+f"(d[64]), "+f"(d[65]), "+f"(d[66]), "+f"(d[67]), "+f"(d[68]), "+f"(d[69]), "+f"(d[70]), "+f"(d[71]),
          "+f"(d[72]), "+f"(d[73]), "+f"(d[74]), "+f"(d[75]), "+f"(d[76]), "+f"(d[77]), "+f"(d[78]), "+f"(d[79]),
          "+f"(d[80]), "+f"(d[81]), "+f"(d[82]), "+f"(d[83]), "+f"(d[84]), "+f"(d[85]), "+f"(d[86]), "+f"(d[87]),
          "+f"(d[88]), "+f"(d[89]), "+f"(d[90]), "+f"(d[91]), "+f"(d[92]), "+f"(d[93]), "+f"(d[94]), "+f"(d[95]),
          "+f"(d[96]), "+f"(d[97]), "+f"(d[98]), "+f"(d[99]), "+f"(d[100]), "+f"(d[101]), "+f"(d[102]), "+f"(d[103]),
          "+f"(d[104]), "+f"(d[105]), "+f"(d[106]), "+f"(d[107]), "+f"(d[108]), "+f"(d[109]), "+f"(d[110]), "+f"(d[111]),
          "+f"(d[112]), "+f"(d[113]), "+f"(d[114]), "+f"(d[115]), "+f"(d[116]), "+f"(d[117]), "+f"(d[118]), "+f"(d[119]),
          "+f"(d[120]), "+f"(d[121]), "+f"(d[122]), "+f"(d[123]), "+f"(d[124]), "+f"(d[125]), "+f"(d[126]), "+f"(d[127])
        : "r"(a[0]), "r"(a[1]), "r"(a[2]), "r"(a[3]), "r"(db), "r"(acc));
}
__device__ __forceinline__ void wgmma_rs_n64(float* d, const uint32_t* a, uint32_t db, int acc) {
    asm volatile("{\n.reg .pred p;\n.reg .b64 dd;\nsetp.ne.b32 p, %37, 0;\nmov.b64 dd, {%36, 0x40000040};\n"
        "wgmma.mma_async.sync.aligned.m64n64k16.f32.bf16.bf16 "
        "{%0, %1, %2, %3, %4, %5, %6, %7, %8, %9, %10, %11, %12, %13, %14, %15, "
        "%16, %17, %18, %19, %20, %21, %22, %23, %24, %25, %26, %27, %28, %29, %30, %31}, "
        "{%32, %33, %34, %35}, dd, p, 1, 1, 1;\n}\n"
        : "+f"(d[0]), "+f"(d[1]), "+f"(d[2]), "+f"(d[3]), "+f"(d[4]), "+f"(d[5]), "+f"(d[6]), "+f"(d[7]),
          "+f"(d[8]), "+f"(d[9]), "+f"(d[10]), "+f"(d[11]), "+f"(d[12]), "+f"(d[13]), "+f"(d[14]), "+f"(d[15]),
          "+f"(d[16]), "+f"(d[17]), "+f"(d[18]), "+f"(d[19]), "+f"(d[20]), "+f"(d[21]), "+f"(d[22]), "+f"(d[23]),
          "+f"(d[24]), "+f"(d[25]), "+f"(d[26]), "+f"(d[27]), "+f"(d[28]), "+f"(d[29]), "+f"(d[30]), "+f"(d[31])
        : "r"(a[0]), "r"(a[1]), "r"(a[2]), "r"(a[3]), "r"(db), "r"(acc));
}
__device__ __forceinline__ void wgmma_rs_n64k(float* d, const uint32_t* a, uint32_t db, int acc) {
    asm volatile("{\n.reg .pred p;\n.reg .b64 dd;\nsetp.ne.b32 p, %37, 0;\nmov.b64 dd, {%36, 0x00000010};\n"
        "wgmma.mma_async.sync.aligned.m64n64k16.f32.bf16.bf16 "
        "{%0, %1, %2, %3, %4, %5, %6, %7, %8, %9, %10, %11, %12, %13, %14, %15, "
        "%16, %17, %18, %19, %20, %21, %22, %23, %24, %25, %26, %27, %28, %29, %30, %31}, "
        "{%32, %33, %34, %35}, dd, p, 1, 1, 0;\n}\n"
        : "+f"(d[0]), "+f"(d[1]), "+f"(d[2]), "+f"(d[3]), "+f"(d[4]), "+f"(d[5]), "+f"(d[6]), "+f"(d[7]),
          "+f"(d[8]), "+f"(d[9]), "+f"(d[10]), "+f"(d[11]), "+f"(d[12]), "+f"(d[13]), "+f"(d[14]), "+f"(d[15]),
          "+f"(d[16]), "+f"(d[17]), "+f"(d[18]), "+f"(d[19]), "+f"(d[20]), "+f"(d[21]), "+f"(d[22]), "+f"(d[23]),
          "+f"(d[24]), "+f"(d[25]), "+f"(d[26]), "+f"(d[27]), "+f"(d[28]), "+f"(d[29]), "+f"(d[30]), "+f"(d[31])
        : "r"(a[0]), "r"(a[1]), "r"(a[2]), "r"(a[3]), "r"(db), "r"(acc));
}
__device__ __forceinline__ void wgmma_rs_n128(float* d, const uint32_t* a, uint32_t db, int acc) {
    asm volatile("{\n.reg .pred p;\n.reg .b64 dd;\nsetp.ne.b32 p, %69, 0;\nmov.b64 dd, {%68, 0x40000040};\n"
        "wgmma.mma_async.sync.aligned.m64n128k16.f32.bf16.bf16 "
        "{%0, %1, %2, %3, %4, %5, %6, %7, %8, %9, %10, %11, %12, %13, %14, %15, "
        "%16, %17, %18, %19, %20, %21, %22, %23, %24, %25, %26, %27, %28, %29, %30, %31, "
        "%32, %33, %34, %35, %36, %37, %38, %39, %40, %41, %42, %43, %44, %45, %46, %47, "
        "%48, %49, %50, %51, %52, %53, %54, %55, %56, %57, %58, %59, %60, %61, %62, %63}, "
        "{%64, %65, %66, %67}, dd, p, 1, 1, 1;\n}\n"
        : "+f"(d[0]), "+f"(d[1]), "+f"(d[2]), "+f"(d[3]), "+f"(d[4]), "+f"(d[5]), "+f"(d[6]), "+f"(d[7]),
          "+f"(d[8]), "+f"(d[9]), "+f"(d[10]), "+f"(d[11]), "+f"(d[12]), "+f"(d[13]), "+f"(d[14]), "+f"(d[15]),
          "+f"(d[16]), "+f"(d[17]), "+f"(d[18]), "+f"(d[19]), "+f"(d[20]), "+f"(d[21]), "+f"(d[22]), "+f"(d[23]),
          "+f"(d[24]), "+f"(d[25]), "+f"(d[26]), "+f"(d[27]), "+f"(d[28]), "+f"(d[29]), "+f"(d[30]), "+f"(d[31]),
          "+f"(d[32]), "+f"(d[33]), "+f"(d[34]), "+f"(d[35]), "+f"(d[36]), "+f"(d[37]), "+f"(d[38]), "+f"(d[39]),
          "+f"(d[40]), "+f"(d[41]), "+f"(d[42]), "+f"(d[43]), "+f"(d[44]), "+f"(d[45]), "+f"(d[46]), "+f"(d[47]),
          "+f"(d[48]), "+f"(d[49]), "+f"(d[50]), "+f"(d[51]), "+f"(d[52]), "+f"(d[53]), "+f"(d[54]), "+f"(d[55]),
          "+f"(d[56]), "+f"(d[57]), "+f"(d[58]), "+f"(d[59]), "+f"(d[60]), "+f"(d[61]), "+f"(d[62]), "+f"(d[63])
        : "r"(a[0]), "r"(a[1]), "r"(a[2]), "r"(a[3]), "r"(db), "r"(acc));
}

__device__ __forceinline__ uint32_t clk() { uint32_t c; asm volatile("mov.u32 %0, %%clock;" : "=r"(c) :: "memory"); return c; }
__device__ __forceinline__ bool elect_one() {
    uint32_t p;
    asm volatile("{\n.reg .pred p;\nelect.sync _|p, 0xffffffff;\nselp.u32 %0, 1, 0, p;\n}\n" : "=r"(p));
    return p;
}
__device__ __forceinline__ void bar_sync(uint32_t id, uint32_t n) { asm volatile("bar.sync %0, %1;" :: "r"(id), "r"(n) : "memory"); }
__device__ __forceinline__ void bar_arrive(uint32_t id, uint32_t n) { asm volatile("bar.arrive %0, %1;" :: "r"(id), "r"(n) : "memory"); }

__device__ __forceinline__ void mbar_init(uint32_t bar, uint32_t cnt) { asm volatile("mbarrier.init.shared::cta.b64 [%0], %1;" :: "r"(bar), "r"(cnt) : "memory"); }
__device__ __forceinline__ void mbar_init_fence() { asm volatile("fence.mbarrier_init.release.cluster;" ::: "memory"); }
__device__ __forceinline__ void mbar_arrive(uint32_t bar) { asm volatile("mbarrier.arrive.shared::cta.b64 _, [%0];" :: "r"(bar) : "memory"); }
__device__ __forceinline__ void mbar_expect(uint32_t bar, uint32_t bytes) {
    asm volatile("mbarrier.arrive.expect_tx.shared::cta.b64 _, [%0], %1;" :: "r"(bar), "r"(bytes) : "memory");
}
__device__ __forceinline__ bool mbar_test(uint32_t bar, uint32_t ph) {
    uint32_t ok;
    asm volatile("{\n.reg .pred p;\nmbarrier.test_wait.parity.shared::cta.b64 p, [%1], %2;\nselp.u32 %0, 1, 0, p;\n}\n" : "=r"(ok) : "r"(bar), "r"(ph) : "memory");
    return ok;
}
__device__ __forceinline__ void mbar_wait(uint32_t bar, uint32_t ph) {
    asm volatile("{\n.reg .pred p;\n.reg .u32 n;\n"
                 "mbarrier.try_wait.parity.shared::cta.b64 p, [%0], %1;\n"
                 "@p bra DONE;\n"
                 "mov.u32 n, 0;\n"
                 "SPIN:\n"
                 "mbarrier.try_wait.parity.shared::cta.b64 p, [%0], %1;\n"
                 "add.u32 n, n, 1;\n"
                 "setp.gt.or.u32 p, n, %2, p;\n"
                 "@!p bra SPIN;\n"
                 "DONE:\n}\n" :: "r"(bar), "r"(ph), "n"(SPIN_LIMIT) : "memory");
}

__device__ __forceinline__ void tma2d(uint32_t dst, const CUtensorMap* m, int c0, int c1, uint32_t bar) {
    asm volatile("cp.async.bulk.tensor.2d.shared::cluster.global.mbarrier::complete_tx::bytes [%0], [%1, {%3, %4}], [%2];"
                 :: "r"(dst), "l"(m), "r"(bar), "r"(c0), "r"(c1) : "memory");
}
__device__ __forceinline__ void tma3d(uint32_t dst, const CUtensorMap* m, int c0, int c1, int c2, uint32_t bar) {
    asm volatile("cp.async.bulk.tensor.3d.shared::cluster.global.mbarrier::complete_tx::bytes [%0], [%1, {%3, %4, %5}], [%2];"
                 :: "r"(dst), "l"(m), "r"(bar), "r"(c0), "r"(c1), "r"(c2) : "memory");
}
__device__ __forceinline__ void tma_store2d(const CUtensorMap* m, uint32_t src, int c0, int c1) {
    asm volatile("cp.async.bulk.tensor.2d.global.shared::cta.bulk_group [%0, {%2, %3}], [%1];" :: "l"(m), "r"(src), "r"(c0), "r"(c1) : "memory");
}
__device__ __forceinline__ void bulk_g2s(uint32_t dst, const void* src, uint32_t bytes, uint32_t bar) {
    asm volatile("cp.async.bulk.shared::cluster.global.mbarrier::complete_tx::bytes [%0], [%1], %2, [%3];"
                 :: "r"(dst), "l"(src), "r"(bytes), "r"(bar) : "memory");
}
__device__ __forceinline__ void prefetch_l2(const void* p) { asm volatile("prefetch.global.L2 [%0];" :: "l"(p)); }
__device__ __forceinline__ void prefetch_map(const CUtensorMap* m) { asm volatile("prefetch.tensormap [%0];" :: "l"(m) : "memory"); }
__device__ __forceinline__ void prefetch_tile(const CUtensorMap* m16, const char* w, int kt, uint32_t bid, bool with_w) {
    asm volatile("cp.async.bulk.prefetch.tensor.2d.L2.global [%0, {%1, %2}];" :: "l"(m16), "r"(kt * BK), "r"(bid * 32) : "memory");
    asm volatile("cp.async.bulk.prefetch.tensor.2d.L2.global [%0, {%1, %2}];" :: "l"(m16), "r"(kt * BK), "r"(bid * 32 + 16) : "memory");
    if (with_w) asm volatile("cp.async.bulk.prefetch.L2.global [%0], 1024;" :: "l"(w + (size_t)kt * 131072 + bid * 1024) : "memory");
}

__device__ __forceinline__ void ldsm4(uint32_t* r, uint32_t addr) {
    asm volatile("ldmatrix.sync.aligned.m8n8.x4.shared.b16 {%0, %1, %2, %3}, [%4];" : "=r"(r[0]), "=r"(r[1]), "=r"(r[2]), "=r"(r[3]) : "r"(addr) : "memory");
}
__device__ __forceinline__ void stsm4(uint32_t addr, uint32_t a, uint32_t b, uint32_t c, uint32_t d) {
    asm volatile("stmatrix.sync.aligned.m8n8.x4.shared.b16 [%0], {%1, %2, %3, %4};" :: "r"(addr), "r"(a), "r"(b), "r"(c), "r"(d) : "memory");
}
__device__ __forceinline__ uint32_t lds32(uint32_t addr) { uint32_t v; asm volatile("ld.shared.u32 %0, [%1];" : "=r"(v) : "r"(addr) : "memory"); return v; }
__device__ __forceinline__ float2 lds64f(uint32_t addr) {
    float2 v; asm volatile("ld.shared.v2.f32 {%0, %1}, [%2];" : "=f"(v.x), "=f"(v.y) : "r"(addr) : "memory"); return v;
}
__device__ __forceinline__ uint4 lds128(uint32_t addr) {
    uint4 v; asm volatile("ld.shared.v4.u32 {%0, %1, %2, %3}, [%4];" : "=r"(v.x), "=r"(v.y), "=r"(v.z), "=r"(v.w) : "r"(addr) : "memory"); return v;
}
__device__ __forceinline__ void sts64f(uint32_t addr, float a, float b) { asm volatile("st.shared.v2.f32 [%0], {%1, %2};" :: "r"(addr), "f"(a), "f"(b) : "memory"); }
__device__ __forceinline__ uint32_t ld_relaxed32(const void* p) {
    uint32_t v; asm volatile("ld.relaxed.gpu.global.u32 %0, [%1];" : "=r"(v) : "l"(p) : "memory"); return v;
}
__device__ __forceinline__ uint2 ld_relaxed64(const void* p) {
    uint2 e; asm volatile("ld.relaxed.gpu.global.b64 %0, [%1];" : "=l"(*(uint64_t*)&e) : "l"(p) : "memory");
    return e;
}

__device__ __forceinline__ uint32_t bmul2(uint32_t a, uint32_t b) { uint32_t r; asm("mul.rn.bf16x2 %0, %1, %2;" : "=r"(r) : "r"(a), "r"(b)); return r; }
__device__ __forceinline__ uint32_t pack2(float lo, float hi) { uint32_t r; asm("cvt.rn.bf16x2.f32 %0, %1, %2;" : "=r"(r) : "f"(hi), "f"(lo)); return r; }
__device__ __forceinline__ float blo(uint32_t v) { return __uint_as_float(v << 16); }
__device__ __forceinline__ float bhi(uint32_t v) { return __uint_as_float(v & 0xffff0000u); }

__device__ __forceinline__ void wg_fence() { asm volatile("wgmma.fence.sync.aligned;" ::: "memory"); }
__device__ __forceinline__ void wg_commit() { asm volatile("wgmma.commit_group.sync.aligned;" ::: "memory"); }
template <int N> __device__ __forceinline__ void wg_wait() { asm volatile("wgmma.wait_group.sync.aligned %0;" :: "n"(N) : "memory"); }
template <int N> __device__ __forceinline__ void fence_regs(float* a) {
#pragma unroll
    for (int i = 0; i < N; i++) asm volatile("" : "+f"(a[i]) :: "memory");
}

__device__ __forceinline__ void split3(float v, uint32_t& p1, uint32_t& p2, uint32_t& p3) {
    p1 = pack2(0.f, v); v -= __uint_as_float(p1);
    p2 = pack2(0.f, v); v -= __uint_as_float(p2);
    p3 = pack2(0.f, v);
}
__device__ __forceinline__ void put_row(uint32_t addr, float v) {
    uint32_t a, b, c; split3(v, a, b, c);
    asm volatile("st.shared.v4.u32 [%0], {%1, %2, %3, %4};"
                 :: "r"(addr), "r"(__byte_perm(a, a, 0x3232)), "r"(__byte_perm(b, b, 0x3232)), "r"(__byte_perm(a, c, 0x7632)), "r"(0) : "memory");
}
__device__ __forceinline__ void put_col(uint2* p, float v) {
    uint32_t a, b, c; split3(v, a, b, c);
    const uint32_t ab = __byte_perm(a, b, 0x7632);
    *(uint4*)p = make_uint4(ab, ab, __byte_perm(c, a, 0x7632), 0);
}

__device__ __forceinline__ void pin4(uint32_t zero, uint32_t* r) {
    asm volatile("{\n.reg .pred p;\nsetp.eq.u32 p, %4, 0;\n@p bra PIN_DONE;\n"
                 "PIN_LOOP:\nshr.u32 %0, %0, 1;\nxor.b32 %1, %1, %0;\nxor.b32 %2, %2, %0;\nxor.b32 %3, %3, %0;\n"
                 "setp.ne.u32 p, %0, 0;\n@p bra PIN_LOOP;\nPIN_DONE:\n}\n"
                 : "+r"(r[0]), "+r"(r[1]), "+r"(r[2]), "+r"(r[3]) : "r"(zero) : "memory");
}
__device__ __forceinline__ void pin8(uint32_t zero, uint32_t* r, float* f) {
    asm volatile("{\n.reg .pred p;\nsetp.eq.u32 p, %12, 0;\n@p bra PIN_DONE;\n"
                 "PIN_LOOP:\nshr.u32 %0, %0, 1;\nxor.b32 %1, %1, %0;\nxor.b32 %2, %2, %0;\nxor.b32 %3, %3, %0;\nxor.b32 %4, %4, %0;\n"
                 "xor.b32 %5, %5, %0;\nxor.b32 %6, %6, %0;\nxor.b32 %7, %7, %0;\n"
                 "add.f32 %8, %8, %9;\nadd.f32 %9, %9, %10;\nadd.f32 %10, %10, %11;\nadd.f32 %11, %11, %8;\n"
                 "setp.ne.u32 p, %0, 0;\n@p bra PIN_LOOP;\nPIN_DONE:\n}\n"
                 : "+r"(r[0]), "+r"(r[1]), "+r"(r[2]), "+r"(r[3]), "+r"(r[4]), "+r"(r[5]), "+r"(r[6]), "+r"(r[7]),
                   "+f"(f[0]), "+f"(f[1]), "+f"(f[2]), "+f"(f[3])
                 : "r"(zero) : "memory");
}
__device__ __forceinline__ void pin16(uint32_t zero, uint32_t* r) {
    asm volatile("{\n.reg .pred p;\nsetp.eq.u32 p, %16, 0;\n@p bra PIN_DONE;\n"
                 "PIN_LOOP:\nshr.u32 %0, %0, 1;\nxor.b32 %1, %1, %0;\nxor.b32 %2, %2, %0;\nxor.b32 %3, %3, %0;\nxor.b32 %4, %4, %0;\n"
                 "xor.b32 %5, %5, %0;\nxor.b32 %6, %6, %0;\nxor.b32 %7, %7, %0;\nxor.b32 %8, %8, %0;\nxor.b32 %9, %9, %0;\n"
                 "xor.b32 %10, %10, %0;\nxor.b32 %11, %11, %0;\nxor.b32 %12, %12, %0;\nxor.b32 %13, %13, %0;\nxor.b32 %14, %14, %0;\n"
                 "xor.b32 %15, %15, %0;\nsetp.ne.u32 p, %0, 0;\n@p bra PIN_LOOP;\nPIN_DONE:\n}\n"
                 : "+r"(r[0]), "+r"(r[1]), "+r"(r[2]), "+r"(r[3]), "+r"(r[4]), "+r"(r[5]), "+r"(r[6]), "+r"(r[7]),
                   "+r"(r[8]), "+r"(r[9]), "+r"(r[10]), "+r"(r[11]), "+r"(r[12]), "+r"(r[13]), "+r"(r[14]), "+r"(r[15])
                 : "r"(zero) : "memory");
}

__device__ __forceinline__ void stats4(const uint32_t* r, float* st) {
    float v;
    v = blo(r[0]); st[0] += v; st[1] = fmaf(v, v, st[1]);
    v = blo(r[1]); st[2] += v; st[3] = fmaf(v, v, st[3]);
    v = bhi(r[0]); st[0] += v; st[1] = fmaf(v, v, st[1]);
    v = bhi(r[1]); st[2] += v; st[3] = fmaf(v, v, st[3]);
    v = blo(r[2]); st[0] += v; st[1] = fmaf(v, v, st[1]);
    v = blo(r[3]); st[2] += v; st[3] = fmaf(v, v, st[3]);
    v = bhi(r[2]); st[0] += v; st[1] = fmaf(v, v, st[1]);
    v = bhi(r[3]); st[2] += v; st[3] = fmaf(v, v, st[3]);
}
__device__ __forceinline__ void scale16(uint32_t* a, const uint32_t* r, const uint32_t* g) {
#pragma unroll
    for (int i = 0; i < 16; i++) a[i] = bmul2(r[i], g[(i >> 2) * 2 + ((i >> 1) & 1)]);
}

__device__ __forceinline__ void centred_row(const char* x, const char* gam, const char* bet, const char* w, char* out, uint32_t n0, uint32_t y) {
    const uint32_t lane = threadIdx.x & 31;
    const uint32_t* xr = (const uint32_t*)x;
    float s = 0.f, q = 0.f;
#pragma unroll 1
    for (int i = lane; i < K_ / 2; i += 32) s += blo(xr[i]) + bhi(xr[i]);
#pragma unroll 1
    for (int o = 16; o; o >>= 1) s += __shfl_xor_sync(~0u, s, o);
    const float m = s * (1.f / K_);
#pragma unroll 1
    for (int i = lane; i < K_ / 2; i += 32) { const float a = blo(xr[i]) - m, b = bhi(xr[i]) - m; q = fmaf(a, a, fmaf(b, b, q)); }
#pragma unroll 1
    for (int o = 16; o; o >>= 1) q += __shfl_xor_sync(~0u, q, o);
    const float r = 1.f / sqrtf(q * (1.f / K_) + 1e-5f);
#pragma unroll 1
    for (int i = lane; i < K_ / 2; i += 32) {
        const uint32_t g = ((const uint32_t*)gam)[i], b = ((const uint32_t*)bet)[i];
        sts64f(y + (i >> 8) * STAGE_BYTES + (i & 255) * 8, fmaf((blo(xr[i]) - m) * r, blo(g), blo(b)), fmaf((bhi(xr[i]) - m) * r, bhi(g), bhi(b)));
    }
    __syncwarp();
    float a[8] = {0.f, 0.f, 0.f, 0.f, 0.f, 0.f, 0.f, 0.f};
#pragma unroll 4
    for (int k = 0; k < K_; k++) {
        const float v = __uint_as_float(lds32(y + (k >> 9) * STAGE_BYTES + (k & 511) * 4));
        const uint4 t = *(const uint4*)(w + (size_t)k * 2048 + n0 * 2 + lane * 16);
        a[0] = fmaf(v, blo(t.x), a[0]); a[1] = fmaf(v, bhi(t.x), a[1]); a[2] = fmaf(v, blo(t.y), a[2]); a[3] = fmaf(v, bhi(t.y), a[3]);
        a[4] = fmaf(v, blo(t.z), a[4]); a[5] = fmaf(v, bhi(t.z), a[5]); a[6] = fmaf(v, blo(t.w), a[6]); a[7] = fmaf(v, bhi(t.w), a[7]);
    }
    *(uint4*)(out + n0 * 2 + lane * 16) = make_uint4(pack2(a[0], a[1]), pack2(a[2], a[3]), pack2(a[4], a[5]), pack2(a[6], a[7]));
    __syncwarp();
}

__device__ __forceinline__ uint32_t w_line(uint32_t b, uint32_t t) {
    return (t * 8 + (b >> 4)) * 16 + (b & 3) * 4 + ((b >> 2) & 3);
}

struct Params { const char* x; const char* w; const char* gam; char* out; uint2* xch; uint32_t zero; const char* bet; };

enum { NB_INIT = 0, NB_COL = 1, NB_HELP = 2, NB_SIDE = 3, NB_LEAD = 4, NB_TURN = 5, NB_GAMMA = 7 };

__global__ void __launch_bounds__(384, 1)
lnlin_kernel(const __grid_constant__ Params prm,
             const __grid_constant__ CUtensorMap tmx64, const __grid_constant__ CUtensorMap tmw16,
             const __grid_constant__ CUtensorMap tmw, const __grid_constant__ CUtensorMap tmo,
             const __grid_constant__ CUtensorMap tmx16, const __grid_constant__ CUtensorMap tmxs, const __grid_constant__ CUtensorMap tmwt,
             const __grid_constant__ CUtensorMap tmx) {
    extern __shared__ __align__(1024) uint8_t smem_raw[];
    const uint32_t tid = threadIdx.x, lane = tid & 31;
    uint2* xch = prm.xch;
    const uint32_t zero = prm.zero;
    const uint32_t bid = (blockIdx.x - (blockIdx.x >= 112 ? 2 : 0)) & 127;
    const uint32_t ni = bid & 3, mi = bid >> 2;
    {
        const uint32_t b = blockIdx.x & 127;
        uint32_t ix = (b >> 2) * BM + (b & 3) * 16 + tid, iw = w_line(b, tid), ig = (b & 15) + tid;
        asm volatile("" : "+r"(ix), "+r"(iw), "+r"(ig));
        if (tid < 16) prefetch_l2(prm.x + (size_t)ix * 2048);
        if (tid < 8) prefetch_l2(prm.w + (size_t)iw * 128);
        if (tid < 1) prefetch_l2(prm.gam + (size_t)ig * 128);
    }
    const bool extra = (blockIdx.x | 1) == 113 || blockIdx.x >= 130;
    const uint32_t sb = (uint32_t)__cvta_generic_to_shared(smem_raw);
    const uint32_t bar_full = sb + OFF_BAR;
    const uint32_t bar_empty = bar_full + 32;
    const uint32_t bar_norm = bar_full + 64;
    const uint32_t bar_part = bar_full + 72;
    const uint32_t bar_tail = bar_full + 144;
    const uint32_t bar_w1 = bar_full + 208;
    const uint32_t bar_xa = bar_full + 216;
    const uint32_t c_start = clk();
    if ((tid >> 5) == 7 && !extra) {
        if (elect_one()) {
            mbar_init(bar_xa, 1); mbar_init(bar_full, 1); mbar_init(bar_xa + 8, 1); mbar_init(bar_w1, 1);
            mbar_init_fence();
        }
        __syncwarp();
        bar_arrive(NB_INIT, 384);
        if (elect_one()) {
            mbar_expect(bar_xa, A_BYTES / 2 + 8192);
            tma2d(sb, &tmx64, 0, mi * BM, bar_xa);
            tma3d(sb + A_BYTES, &tmw16, 0, ni * 16, ni * 4, bar_xa);
            mbar_expect(bar_w1, 8192);
            tma3d(sb + A_BYTES + 8192, &tmw16, 0, (1 ^ ni) * 16, ni * 4, bar_w1);
            mbar_expect(bar_full, 16384);
            tma3d(sb + A_BYTES + 16384, &tmw16, 0, (2 ^ ni) * 16, ni * 4, bar_full);
            tma3d(sb + A_BYTES + 24576, &tmw16, 0, (3 ^ ni) * 16, ni * 4, bar_full);
            mbar_expect(bar_xa + 8, A_BYTES / 2);
            tma2d(sb + A_BYTES / 2, &tmx64, 0, mi * BM + 64, bar_xa + 8);
        }
    }
    if (tid - 32 < 128)
        asm volatile("cp.async.cg.shared.global [%0], [%1], 16;" :: "r"(SMEM_BASE + OFF_G + (tid - 32) * 16), "l"(prm.gam + (size_t)(tid - 32) * 16) : "memory");
    if ((tid >> 5) == 9 && !extra) {
        if (elect_one()) {
#pragma unroll
            for (int i = 1; i < 26; i++) mbar_init(bar_full + 8 * i, i < 4 ? 1 : i < 8 ? 8 : i == 8 ? 128 : i == 9 ? 8 : i >= 18 ? 4 : 1);
#pragma unroll
            for (int i = 2; i < 8; i++) mbar_init(bar_xa + 8 * i, 1);
            mbar_init_fence();
        }
    } else if (tid >= 192 && tid < 208) {
        while (clk() - c_start < T_PF_XB0) {}
        prefetch_l2(prm.x + (size_t)(mi * BM + 64 + ni * 16 + lane) * 2048);
    }
    const uint32_t warp = __shfl_sync(~0u, tid >> 5, 0);

    if (extra) {
        const uint32_t e = (blockIdx.x & 1) + (blockIdx.x >= 130 ? 2 : 0);
        const uint32_t bar_free = bar_full + 48, bar_beta = bar_full + 96, bar_seq = bar_full + 104;
        const uint32_t c0 = clk();
        if (tid == 0) {
#pragma unroll
            for (int i = 0; i < 14; i++) mbar_init(bar_full + 8 * i, i >= 6 && i < 12 ? 8 : 1);
            mbar_init_fence();
        }
        __syncthreads();
        if (warp == 8) {
            if (elect_one()) {
                mbar_expect(bar_beta, 2048);
                bulk_g2s(sb + OFF_B, prm.bet, 2048, bar_beta);
                uint32_t s = 0, ph = 1;
#pragma unroll 1
                for (int i = 0; i < 16; i++) {
                    if (i < 6) { while (clk() - c0 < (i ? T_COL0 + T_COL * i : 0)) {} } else mbar_wait(bar_free + 8 * s, ph);
                    mbar_expect(bar_full + 8 * s, B_BYTES);
                    tma3d(sb + s * B_BYTES, &tmw, 0, ((i >> 1) + (i & 1) * 8) * BK, e * 4, bar_full + 8 * s);
                    if (i == 7) { mbar_expect(bar_seq, 16); bulk_g2s(sb + OFF_SIDE, xch + XCH_FLAG + e * 16, 16, bar_seq); }
                    if (++s == 6) { s = 0; ph ^= 1; }
                }
            }
        } else if (warp < 8) {
            float acc[64];
            const uint32_t ga = sb + OFF_G + (lane & 1) * 2048 + (lane >> 3) * 16;
            uint32_t s = 0, ph = 0;
            asm volatile("cp.async.wait_all;" ::: "memory");
            bar_sync(NB_COL, 256);
            mbar_wait(bar_beta, 0);
#pragma unroll 1
            for (int i = 0; i < 8; i++) {
#pragma unroll
                for (int h = 0; h < 2; h++) {
                    uint32_t gg[8];
                    const uint32_t go = ga + (i + h * 8) * 128;
                    ldsm4(gg, go); ldsm4(gg + 4, go + 64);
                    mbar_wait(bar_full + 8 * s, ph);
                    wg_fence();
#pragma unroll
                    for (int kk = 0; kk < 4; kk++) {
                        const uint32_t a[4] = {gg[2 * kk], 0, gg[2 * kk + 1], 0};
                        wgmma_rs_n128(acc, a, (((SMEM_BASE + kk * 2048) >> 4) | ((8192 >> 4) << 16)) + (s * 2 + (warp >> 2)) * 1024, i | h | kk);
                    }
                    wg_commit();
                    wg_wait<1>();
                    if ((i | h) && elect_one()) mbar_arrive(bar_free + 8 * (s ? s - 1 : 5));
                    if (++s == 6) { s = 0; ph ^= 1; }
                }
            }
            wg_wait<0>();
            mbar_wait(bar_seq, 0);
            fence_regs<64>(acc);
            const uint32_t j = (warp & 3) * 4 + (lane >> 3);
            float v0 = acc[0], v1 = acc[4];
#pragma unroll
            for (int i = 1; i < 16; i++) if (j == i) { v0 = acc[8 * (i >> 1) + (i & 1)]; v1 = acc[8 * (i >> 1) + 4 + (i & 1)]; }
            const uint32_t slot = ((warp >> 2) * 16 + (j & ~1u)) * 16 + ((lane >> 2) & 1) * 8 + (lane & 3) * 2 + (j & 1);
            put_col(xch + XCH_COL + e * 1024 + slot * 2, v0);
            put_col(xch + XCH_COL + e * 1024 + slot * 2 + 32, v1);
            bar_sync(NB_COL, 256);
            if (tid == 0) asm volatile("st.release.gpu.global.u32 [%0], %1;" :: "l"(xch + XCH_FLAG + e * 16), "r"(lds32(sb + OFF_SIDE) ^ 1) : "memory");
        }
        return;
    }

    if (warp < 8) {
        asm volatile("setmaxnreg.inc.sync.aligned.u32 232;");
        float acc[128];
        uint32_t ax[4];
        {
            const uint32_t a_off = (sb + (warp * 16 + (lane & 15)) * 128 + (((lane >> 4) ^ (lane & 7)) << 4)) ^ (ni << 5);
#pragma unroll
            for (int kk = 0; kk < 4; kk++) ax[kk] = __shfl_sync(~0u, a_off ^ (kk << 5), lane);
        }
        const uint32_t g0 = __shfl_sync(~0u, (sb + OFF_G + (lane >> 3) * 16) ^ (ni << 5), lane), g1 = __shfl_sync(~0u, g0 ^ 64, lane);
        const uint32_t t8 = __shfl_sync(~0u, tid * 8, lane);
        constexpr uint32_t DESC0 = ((SMEM_BASE + A_BYTES) >> 4) | ((8192 >> 4) << 16);
        constexpr uint32_t DESCB = ((SMEM_BASE + OFF_BB) >> 4) | ((128 >> 4) << 16);
        constexpr int SD = STAGE_BYTES >> 4;
        uint32_t dk[4];
#pragma unroll
        for (int kk = 0; kk < 4; kk++) dk[kk] = DESC0 + ((kk ^ ni) << 7);
        uint32_t a0[16], a1[16], a2[16], a3[16];
        float st[4] = {0.f, 0.f, 0.f, 0.f};
        auto refill_tail = [&](int s) {
            mbar_wait(bar_empty + 8 * s, 0);
            if (elect_one()) {
                mbar_expect(bar_full + 8 * s, B_BYTES);
                tma2d(sb + s * STAGE_BYTES + A_BYTES, &tmwt, ni * BN + s * 64, 768, bar_full + 8 * s);
            }
        };
        uint32_t gt[32];
        if (warp < 7) bar_sync(NB_INIT, 384);
        asm volatile("cp.async.wait_all;" ::: "memory");
        bar_sync(NB_GAMMA, 256);
#pragma unroll
        for (int i = 0; i < 8; i++) ldsm4(gt + 4 * i, sb + OFF_G + 1536 + i * 64 + (lane >> 3) * 16);
        uint32_t prev[4];
        {
            uint32_t gg[8], r[16];
            ldsm4(gg, g0); ldsm4(gg + 4, g1);
            constexpr uint32_t DW0 = ((SMEM_BASE + A_BYTES) >> 4) | ((2048 >> 4) << 16);
            pin8(zero, gg, st);
            mbar_wait(bar_xa + (warp >> 2) * 8, 0);
#pragma unroll
            for (int kk = 0; kk < 4; kk++) ldsm4(r + 4 * kk, ax[kk]);
            if (warp >= 4) bar_sync(NB_LEAD, 256);
#pragma unroll
            for (int i = 0; i < 4; i++) a0[i] = bmul2(r[i], gg[i >> 1]);
            wg_fence();
            wgmma_rs_n256(acc, a0, DW0, 0);
            pin8(zero, gg, st);
#pragma unroll
            for (int i = 4; i < 16; i++) a0[i] = bmul2(r[i], gg[(i >> 2) * 2 + ((i >> 1) & 1)]);
            mbar_wait(bar_w1, 0);
            wg_fence();
            wgmma_rs_n256(acc, a0 + 4, DW0 + 512, 1);
            mbar_wait(bar_full, 0);
            wg_fence();
            wgmma_rs_n256(acc, a0 + 8, DW0 + 1024, 1);
            wgmma_rs_n256(acc, a0 + 12, DW0 + 1536, 1);
            wg_commit();
            if (warp < 4) bar_arrive(NB_LEAD, 256);
#pragma unroll
            for (int i = 0; i < 4; i++) prev[i] = r[i];
        }
        bool ready = false;
        auto tail_prep = [&](uint32_t* a, int t) {
            uint32_t r[16];
            mbar_wait(bar_tail + 8 * t + (warp >> 2) * 32, 0);
#pragma unroll
            for (int kk = 0; kk < 4; kk++) ldsm4(r + 4 * kk, ax[kk] + t * STAGE_BYTES);
            scale16(a, r, gt + 8 * t);
            pin16(zero, a);
        };
#pragma unroll
        for (int kt = 1; kt < 12; kt++) {
            const int j = kt & 3;
            uint32_t* a = (kt & 1) ? a1 : a0;
            if (kt < 4) mbar_wait(bar_xa + 16 * j + (warp >> 2) * 8, 0);
            else if (!ready) mbar_wait(bar_full + 8 * j, (kt >> 2) & 1);
            uint32_t gg[8], r[16];
            ldsm4(r, ax[0] + j * STAGE_BYTES); ldsm4(gg, g0 + kt * 128); ldsm4(r + 4, ax[1] + j * STAGE_BYTES);
            ldsm4(r + 8, ax[2] + j * STAGE_BYTES); ldsm4(gg + 4, g1 + kt * 128); ldsm4(r + 12, ax[3] + j * STAGE_BYTES);
            if (kt <= LASTC) {
                pin4(zero, prev);
                stats4(prev, st);
                pin8(zero, gg, st);
#pragma unroll
                for (int i = 0; i < 4; i++) prev[i] = r[i];
            }
            if (kt == LASTC) {
                stats4(prev, st);
                const bool up = t8 & 16;
                const float s = (up ? st[2] : st[0]) + __shfl_xor_sync(~0u, up ? st[0] : st[2], 2);
                const float q = (up ? st[3] : st[1]) + __shfl_xor_sync(~0u, up ? st[1] : st[3], 2);
                sts64f(sb + OFF_PART + t8, s, q);
                __syncwarp();
                if (elect_one()) mbar_arrive(bar_part);
            }
            scale16(a, r, gg);
            if (kt < 4) { pin16(zero, a); mbar_wait(bar_full + 8 * j, 0); }
            wg_fence();
#pragma unroll
            for (int kk = 0; kk < 4; kk++) wgmma_rs_n256(acc, a + 4 * kk, dk[kk] + j * SD, 1);
            wg_commit();
            if (kt >= 8) {
                if (elect_one()) {
                    const uint32_t bar = bar_tail + 8 * j + (warp >> 2) * 32;
                    mbar_expect(bar, 2048);
                    tma2d(sb + j * STAGE_BYTES + warp * 2048, &tmx16, (kt + 4) * BK, mi * BM + warp * 16, bar);
                }
            }
            if (kt == 11) {
#pragma unroll
                for (int kk = 0; kk < 4; kk++) ax[kk] ^= ni << 5;
                tail_prep(a2, 0);
            }
            if (kt >= 3) ready = mbar_test(bar_full + 8 * ((kt + 1) & 3), ((kt + 1) >> 2) & 1);
            wg_wait<1>();
            const int s = (kt - 1) & 3;
            if (elect_one()) mbar_arrive(bar_empty + 8 * s);
            if (warp == 4 + j) {
                if (kt > 8) refill_tail(s);
                else {
                    mbar_wait(bar_empty + 8 * s, ((kt - 1) >> 2) & 1);
                    if (elect_one()) {
                        mbar_expect(bar_full + 8 * s, STAGE_BYTES);
                        tma2d(sb + s * STAGE_BYTES, &tmx, (kt + 3) * BK, mi * BM, bar_full + 8 * s);
                        tma3d(sb + s * STAGE_BYTES + A_BYTES, &tmw, 0, (kt + 3) * BK, ni * 4, bar_full + 8 * s);
                        if (kt + 4 <= LASTC) prefetch_tile(&tmx16, prm.w, kt + 4, bid, kt + 4 < 8);
                    }
                }
            }
        }
        const uint32_t ln = (t8 >> 3) & 31;
        tail_prep(a3, 1);
        tail_prep(a0, 2);
        {
            uint32_t r[16];
            if (!ready) mbar_wait(bar_full, 1);
            mbar_wait(bar_full + 8, 1);
            mbar_wait(bar_tail + 24 + (warp >> 2) * 32, 0);
            wg_wait<0>();
#pragma unroll
            for (int kk = 0; kk < 4; kk++) ldsm4(r + 4 * kk, ax[kk] + 3 * STAGE_BYTES);
            if (elect_one()) mbar_arrive(bar_empty + 24);
            scale16(a1, r, gt + 24);
        }
#pragma unroll
        for (int i = 0; i < 128; i++) { float t; asm volatile("mov.b32 %0, %1;" : "=f"(t) : "f"(acc[i])); acc[i] = t; }
        auto mma_q = [&](int q, int i) {
            const uint32_t* a = i < 4 ? a2 : i < 8 ? a3 : i < 12 ? a0 : a1;
            wgmma_rs_n64(acc + 32 * q, a + 4 * (i & 3), DESC0 + i * 128 + q * SD, 1);
        };
        const uint32_t my_turn = NB_TURN + (warp >> 2), other_turn = NB_TURN + 1 - (warp >> 2);
        if (warp >= 4) bar_sync(my_turn, 256);
        wg_fence();
#pragma unroll
        for (int i = 0; i < 12; i++) mma_q(0, i);
#pragma unroll
        for (int i = 0; i < SKEW; i++) mma_q(1, i);
        wg_commit();
        mbar_wait(bar_norm, 0);
        uint32_t ab[4];
        ldsm4(ab, sb + OFF_AB + (ln >> 4) * 2048 + (warp * 16 + (ln & 15)) * 16);
        const float2 rs = lds64f(sb + OFF_RSTD + (warp * 8 + (ln >> 2)) * 8);
        wg_fence();
#pragma unroll
        for (int i = 12; i < 16; i++) mma_q(0, i);
        wgmma_rs_n64k(acc, ab, DESCB, 1);
        wg_commit();
        bar_arrive(other_turn, 256);
        if (warp == 4) refill_tail(3);
        const uint32_t redo = __ballot_sync(~0u, ((ln & 1) ? rs.y : rs.x) < 0.f);
        auto stage = [&](int q) {
            wg_wait<0>();
            fence_regs<32>(acc + 32 * q);
#pragma unroll
            for (int c = 0; c < 4; c++) {
                const float* a = acc + 32 * q + 8 * c;
                stsm4(ax[c] + q * STAGE_BYTES, pack2(rs.x * a[0], rs.x * a[1]), pack2(rs.y * a[2], rs.y * a[3]),
                      pack2(rs.x * a[4], rs.x * a[5]), pack2(rs.y * a[6], rs.y * a[7]));
            }
        };
        auto drain = [&](int q) {
            stage(q);
            asm volatile("fence.proxy.async.shared::cta;" ::: "memory");
            __syncwarp();
            if (elect_one()) tma_store2d(&tmo, sb + q * STAGE_BYTES + warp * 2048, ni * BN + q * 64, mi * BM + warp * 16);
        };
        auto block = [&](int q) {
            wg_fence();
#pragma unroll
            for (int i = (q == 1 ? SKEW : 0); i < 16; i++) mma_q(q, i);
            wgmma_rs_n64k(acc + 32 * q, ab, DESCB + q * 128, 1);
            wg_commit();
        };
#pragma unroll
        for (int q = 0; q < 3; q++) {
            if (q > 0) mbar_wait(bar_full + 8 * (q + 1), 1);
            drain(q);
            bar_sync(my_turn, 256);
            if (q < 2) {
                block(q + 1);
                bar_arrive(other_turn, 256);
            }
        }
        block(3);
        if (warp < 4) {
            bar_arrive(other_turn, 256);
            drain(3);
            asm volatile("cp.async.bulk.commit_group;" ::: "memory");
            asm volatile("cp.async.bulk.wait_group.read 0;" ::: "memory");
            if (!redo) asm volatile("exit;");
        } else {
            const uint64_t og = (uint64_t)(prm.out + (size_t)(mi * BM + warp * 16 + (ln >> 3)) * 2048 + ni * 512 + 384 + (ln & 7) * 16);
            const uint32_t os = sb + 3 * STAGE_BYTES + warp * 2048 + (ln >> 3) * 128 + (((ln & 7) ^ (ln >> 3)) << 4);
            uint32_t ad[4] = {os, os ^ 64, (uint32_t)og, (uint32_t)(og >> 32)};
            pin4(zero, ad);
            char* o = (char*)(((uint64_t)ad[3] << 32) | ad[2]);
            asm volatile("cp.async.bulk.commit_group;" ::: "memory");
            asm volatile("cp.async.bulk.wait_group.read 0;" ::: "memory");
            stage(3);
            __syncwarp();
            uint4 v[4];
#pragma unroll
            for (int i = 0; i < 4; i++) v[i] = lds128(ad[i & 1] + i * 512);
#pragma unroll
            for (int i = 0; i < 4; i++)
                asm volatile("st.global.v4.u32 [%0], {%1, %2, %3, %4};" :: "l"(o + i * 8192), "r"(v[i].x), "r"(v[i].y), "r"(v[i].z), "r"(v[i].w) : "memory");
            if (!redo) asm volatile("exit;");
        }
        asm volatile("cp.async.bulk.wait_group 0;" ::: "memory");
        asm volatile("fence.proxy.async;" ::: "memory");
        __syncwarp();
#pragma unroll 1
        for (int i = 0; i < 16; i++) {
            if (!(redo >> ((i & 7) * 4 + (i >> 3)) & 1)) continue;
            const size_t row = (size_t)(mi * BM + warp * 16 + i) * 2048;
            centred_row(prm.x + row, prm.gam, prm.bet, prm.w, prm.out + row, ni * BN, sb + warp * 2048);
        }
    } else {
        asm volatile("setmaxnreg.dec.sync.aligned.u32 40;");
        if (warp == 10) {
            bar_arrive(NB_INIT, 384);
            const char* px = prm.x + (size_t)(mi * BM + ni * 16 + lane) * 2048 + 128;
            while (clk() - c_start < T_PF_XA1) {}
            if (lane < 16) prefetch_l2(px);
            while (clk() - c_start < T_PF_W1) {}
            if (lane < 8) prefetch_l2(prm.w + (size_t)(1024 + bid * 8 + lane) * 128);
            while (clk() - c_start < T_PF_XB1) {}
            if (lane < 16) prefetch_l2(px + 64 * 2048);
        } else {
            bar_sync(NB_INIT, 384);
        }
        if (warp == 11) {
            if (elect_one()) {
#pragma unroll 1
                for (int kt = 1; kt < 4; kt++) {
                    const uint32_t t = T_TILE1 + T_TILE * (kt - 1);
                    while (clk() - c_start < t) {}
                    mbar_expect(bar_xa + 16 * kt, A_BYTES / 2);
                    tma2d(sb + kt * STAGE_BYTES, &tmx64, kt * BK, mi * BM, bar_xa + 16 * kt);
                    while (clk() - c_start < t + T_W) {}
                    mbar_expect(bar_full + 8 * kt, B_BYTES);
                    tma3d(sb + kt * STAGE_BYTES + A_BYTES, &tmw, 0, kt * BK, ni * 4, bar_full + 8 * kt);
                    while (clk() - c_start < t + T_XB) {}
                    mbar_expect(bar_xa + 16 * kt + 8, A_BYTES / 2);
                    tma2d(sb + kt * STAGE_BYTES + A_BYTES / 2, &tmx64, kt * BK, mi * BM + 64, bar_xa + 16 * kt + 8);
                    if (kt < 3) prefetch_map(kt == 1 ? &tmx : &tmxs);
                }
            }
            __syncwarp();
        }
        bar_sync(NB_HELP, 128);

        const uint32_t ht = tid - 256, hw = warp - 8;
        const uint32_t row0 = mi * BM + ni * 32 + hw * 8;
        const uint32_t side = sb + OFF_SIDE + hw * 2 * SLOT, bar_side = bar_full + 80 + 16 * hw;
        const uint2* prow = xch + XCH_ROW + mi * 512 + ht;
        float s0 = 0.f, q0 = 0.f;
        mbar_wait(bar_full + 24, 0);
        if (hw) mbar_wait(bar_full + 8 * (hw - 1), 1);
        if (elect_one()) {
            mbar_expect(bar_side, SLOT + 256);
            tma2d(side, &tmxs, (LASTC + 1) * BK, row0, bar_side);
            bulk_g2s(sb + OFF_SEQ + hw * 256, xch + XCH_ROW + mi * 512 + ni * 128 + hw * 32, 256, bar_side);
            if (hw == 3) { prefetch_map(&tmo); prefetch_map(&tmwt); prefetch_map(&tmx16); }
        }
        mbar_wait(bar_side, 0);
        if (elect_one()) {
            mbar_expect(bar_side + 8, SLOT);
            tma2d(side + SLOT, &tmxs, (LASTC + 1) * BK + NSIDE * 32, row0, bar_side + 8);
        }
        const uint32_t seq = ~lds32(sb + OFF_SEQ + ht * 8) & 1;
#pragma unroll 1
        for (int k = 0; k < 2; k++) {
            if (k) mbar_wait(bar_side + 8, 0);
            const uint32_t a = side + k * SLOT + (lane >> 2) * (NSIDE * 64) + (lane & 3) * 16;
            float s1 = 0.f, q1 = 0.f;
#pragma unroll
            for (int i = 0; i < NSIDE; i++) {
                const uint4 v = lds128(a + i * 64);
                float t;
                t = blo(v.x); s0 += t; q0 = fmaf(t, t, q0); t = bhi(v.x); s1 += t; q1 = fmaf(t, t, q1);
                t = blo(v.y); s0 += t; q0 = fmaf(t, t, q0); t = bhi(v.y); s1 += t; q1 = fmaf(t, t, q1);
                t = blo(v.z); s0 += t; q0 = fmaf(t, t, q0); t = bhi(v.z); s1 += t; q1 = fmaf(t, t, q1);
                t = blo(v.w); s0 += t; q0 = fmaf(t, t, q0); t = bhi(v.w); s1 += t; q1 = fmaf(t, t, q1);
            }
            s0 += s1; q0 += q1;
        }
#pragma unroll
        for (int o = 1; o < 4; o <<= 1) { s0 += __shfl_xor_sync(~0u, s0, o); q0 += __shfl_xor_sync(~0u, q0, o); }
        if ((lane & 3) == 0) sts64f(sb + OFF_RED + 256 + (hw * 8 + (lane >> 2)) * 8, s0, q0);
        bar_sync(NB_SIDE, 128);

        float2 own = lds64f(sb + OFF_RED + 256 + lane * 8);
        if (hw != ni) { own.x = 0.f; own.y = 0.f; }
        mbar_wait(bar_part, 0);
        uint32_t flag = ld_relaxed32(xch + XCH_FLAG + ni * 16);
        {
            const uint4 p = lds128(sb + OFF_PART + ((ht >> 4) * 32 + (ht & 7) * 4) * 8 + (ht & 8) * 2);
            own.x += __uint_as_float(p.x) + __uint_as_float(p.z); own.y += __uint_as_float(p.y) + __uint_as_float(p.w);
        }
        own.x = __uint_as_float(__float_as_uint(own.x) & ~1u);
        asm volatile("st.relaxed.gpu.global.b64 [%0], %1;"
                     :: "l"(prow + ni * 128), "l"(((uint64_t)__float_as_uint(own.y) << 32) | __float_as_uint(own.x) | seq) : "memory");
        uint32_t n = 0;
        while (flag != seq && ++n < POLL_LIMIT) flag = ld_relaxed32(xch + XCH_FLAG + ni * 16);
        __syncwarp();
        if (elect_one()) {
            asm volatile("fence.acquire.gpu;" ::: "memory");
            asm volatile("fence.proxy.async.global;" ::: "memory");
            mbar_expect(bar_side, 2048);
            bulk_g2s(sb + OFF_BB + hw * 2048, xch + XCH_COL + ni * 1024 + hw * 256, 2048, bar_side);
        }
        uint2 e0 = ld_relaxed64(prow + (1 ^ ni) * 128), e1 = ld_relaxed64(prow + (2 ^ ni) * 128), e2 = ld_relaxed64(prow + (3 ^ ni) * 128);
        while ((((e0.x ^ seq) | (e1.x ^ seq) | (e2.x ^ seq)) & 1) && ++n < POLL_LIMIT) {
            e0 = ld_relaxed64(prow + (1 ^ ni) * 128); e1 = ld_relaxed64(prow + (2 ^ ni) * 128); e2 = ld_relaxed64(prow + (3 ^ ni) * 128);
        }
        const float ss = (own.x + __uint_as_float(e0.x & ~1u)) + (__uint_as_float(e1.x & ~1u) + __uint_as_float(e2.x & ~1u));
        const float qq = (own.y + __uint_as_float(e0.y)) + (__uint_as_float(e1.y) + __uint_as_float(e2.y));
        const float m = ss * (1.f / K_);
        const float sd = sqrtf(fmaxf(qq * (1.f / K_) - m * m, 0.f) + 1e-5f);
        const float rstd = 1.f / sd;
        put_row(sb + OFF_AB + ht * 16, -m);
        put_row(sb + OFF_AB + 2048 + ht * 16, sd);
        asm volatile("st.shared.f32 [%0], %1;" :: "r"(sb + OFF_RSTD + ((ht & ~15u) + (ht & 7) * 2 + ((ht >> 3) & 1)) * 4),
                     "f"(fabsf(m) <= MEAN_LIMIT * sd && sd < 1e18f ? rstd : -1.f) : "memory");
        mbar_wait(bar_side, 1);
        mbar_arrive(bar_norm);
    }
}

__global__ void __launch_bounds__(256)
lnlin_fallback(const __nv_bfloat16* __restrict__ x, const __nv_bfloat16* __restrict__ g, const __nv_bfloat16* __restrict__ b,
               const __nv_bfloat16* __restrict__ w, __nv_bfloat16* __restrict__ out) {
    __shared__ float y[8][K_];
    const int warp = threadIdx.x >> 5, lane = threadIdx.x & 31;
    const __nv_bfloat16* xr = x + (size_t)(blockIdx.x * 8 + warp) * K_;
    float s = 0.f;
    for (int k = lane; k < K_; k += 32) s += __bfloat162float(xr[k]);
    for (int o = 16; o; o >>= 1) s += __shfl_xor_sync(~0u, s, o);
    const float m = s * (1.f / K_);
    float q = 0.f;
    for (int k = lane; k < K_; k += 32) { const float d = __bfloat162float(xr[k]) - m; q = fmaf(d, d, q); }
    for (int o = 16; o; o >>= 1) q += __shfl_xor_sync(~0u, q, o);
    const float r = 1.f / sqrtf(q * (1.f / K_) + 1e-5f);
    for (int k = lane; k < K_; k += 32) y[warp][k] = (__bfloat162float(xr[k]) - m) * r * __bfloat162float(g[k]) + __bfloat162float(b[k]);
    __syncthreads();
    for (int n = threadIdx.x; n < N_; n += 256) {
        float a[8] = {0.f, 0.f, 0.f, 0.f, 0.f, 0.f, 0.f, 0.f};
        for (int k = 0; k < K_; k++) {
            const float wv = __bfloat162float(w[(size_t)k * N_ + n]);
#pragma unroll
            for (int i = 0; i < 8; i++) a[i] = fmaf(y[i][k], wv, a[i]);
        }
#pragma unroll
        for (int i = 0; i < 8; i++) out[(size_t)(blockIdx.x * 8 + i) * N_ + n] = __float2bfloat16(a[i]);
    }
}

typedef CUresult (*EncodeFn)(CUtensorMap*, CUtensorMapDataType, cuuint32_t, void*, const cuuint64_t*, const cuuint64_t*, const cuuint32_t*,
                             const cuuint32_t*, CUtensorMapInterleave, CUtensorMapSwizzle, CUtensorMapL2promotion, CUtensorMapFloatOOBfill);

}

extern "C" void kernel_launch(void* const* d_in, const int* in_sizes, int n_in, void* d_out, int out_size) {
    static bool queried = false, fused = false;
    static EncodeFn enc = nullptr;
    static void* xch = nullptr;
    if (!queried) {
        queried = true;
        int dev = 0, sms = 0, reserved = 0, per_sm = 0;
        cudaFuncAttributes fa = {};
        cudaDriverEntryPointQueryResult qr;
        cudaGetDevice(&dev);
        cudaDeviceGetAttribute(&sms, cudaDevAttrMultiProcessorCount, dev);
        cudaDeviceGetAttribute(&reserved, cudaDevAttrReservedSharedMemoryPerBlock, dev);
        cudaGetDriverEntryPoint("cuTensorMapEncodeTiled", (void**)&enc, cudaEnableDefault, &qr);
        cudaFuncSetAttribute(lnlin_kernel, cudaFuncAttributeMaxDynamicSharedMemorySize, SMEM_BYTES);
        cudaFuncGetAttributes(&fa, lnlin_kernel);
        cudaOccupancyMaxActiveBlocksPerMultiprocessor(&per_sm, lnlin_kernel, 384, SMEM_BYTES);
        cudaGetSymbolAddress(&xch, g_xch);
        fused = enc && xch && sms * per_sm >= 132 && reserved == (int)SMEM_BASE && fa.sharedSizeBytes == 0;
        (void)cudaGetLastError();
    }
    if (!fused) {
        lnlin_fallback<<<M_ / 8, 256, 0, cudaStreamPerThread>>>((const __nv_bfloat16*)d_in[0], (const __nv_bfloat16*)d_in[1], (const __nv_bfloat16*)d_in[2],
                                                                (const __nv_bfloat16*)d_in[3], (__nv_bfloat16*)d_out);
        return;
    }
    CUtensorMap tmx, tmx64, tmx16, tmxs, tmw, tmw16, tmwt, tmo;
    auto map2 = [&](CUtensorMap* m, void* p, uint32_t rows, uint32_t bx, uint32_t by, CUtensorMapSwizzle sw, CUtensorMapL2promotion pr) {
        cuuint64_t dim[2] = {1024, rows}, str[1] = {2048};
        cuuint32_t box[2] = {bx, by}, es[2] = {1, 1};
        enc(m, CU_TENSOR_MAP_DATA_TYPE_BFLOAT16, 2, p, dim, str, box, es, CU_TENSOR_MAP_INTERLEAVE_NONE, sw, pr, CU_TENSOR_MAP_FLOAT_OOB_FILL_NONE);
    };
    map2(&tmx, d_in[0], M_, BK, BM, CU_TENSOR_MAP_SWIZZLE_128B, CU_TENSOR_MAP_L2_PROMOTION_L2_128B);
    map2(&tmx64, d_in[0], M_, BK, 64, CU_TENSOR_MAP_SWIZZLE_128B, CU_TENSOR_MAP_L2_PROMOTION_L2_128B);
    map2(&tmx16, d_in[0], M_, BK, 16, CU_TENSOR_MAP_SWIZZLE_128B, CU_TENSOR_MAP_L2_PROMOTION_L2_128B);
    map2(&tmxs, d_in[0], M_, NSIDE * 32, 8, CU_TENSOR_MAP_SWIZZLE_NONE, CU_TENSOR_MAP_L2_PROMOTION_L2_128B);
    map2(&tmwt, d_in[3], K_, 64, 256, CU_TENSOR_MAP_SWIZZLE_128B, CU_TENSOR_MAP_L2_PROMOTION_L2_128B);
    map2(&tmo, d_out, M_, 64, 16, CU_TENSOR_MAP_SWIZZLE_128B, CU_TENSOR_MAP_L2_PROMOTION_NONE);
    auto map3 = [&](CUtensorMap* m, uint32_t rows) {
        cuuint64_t dim[3] = {64, K_, N_ / 64}, str[2] = {N_ * 2, 128};
        cuuint32_t box[3] = {64, rows, 4}, es[3] = {1, 1, 1};
        enc(m, CU_TENSOR_MAP_DATA_TYPE_BFLOAT16, 3, d_in[3], dim, str, box, es, CU_TENSOR_MAP_INTERLEAVE_NONE, CU_TENSOR_MAP_SWIZZLE_128B,
            CU_TENSOR_MAP_L2_PROMOTION_L2_128B, CU_TENSOR_MAP_FLOAT_OOB_FILL_NONE);
    };
    map3(&tmw, BK);
    map3(&tmw16, 16);
    const Params prm = {(const char*)d_in[0], (const char*)d_in[3], (const char*)d_in[1], (char*)d_out, (uint2*)xch, 0u, (const char*)d_in[2]};
    lnlin_kernel<<<132, 384, SMEM_BYTES, cudaStreamPerThread>>>(prm, tmx64, tmw16, tmw, tmo, tmx16, tmxs, tmwt, tmx);
}
```
